```python
import torch

def _softmax(x, axis=-1):
    return torch.softmax(x, dim=axis)
def _gelu(x):
    return torch.nn.functional.gelu(x, approximate="tanh")
def _silu(x):
    return torch.nn.functional.silu(x)
def _sigmoid(x):
    return torch.sigmoid(x)
def _layernorm(x, axis=-1, eps=1e-5):
    m = x.mean(dim=axis, keepdim=True)
    v = x.var(dim=axis, keepdim=True, unbiased=False)
    return (x - m) / torch.sqrt(v + eps)
def _scatter_add(tgt, idx, src, axis=0):
    return tgt.clone().index_add_(axis, idx, src)
def _segment_sum(src, seg, n):
    out = torch.zeros((n,) + src.shape[1:], dtype=src.dtype)
    return out.index_add_(0, seg, src)
def _pad(x, pw):
    flat = tuple(v for pair in reversed(pw) for v in pair)
    return torch.nn.functional.pad(x, flat)

kernel_name = 'recurrent_scan__ssm_conv_s5__dense_activation_mish__prompt'

def setup_inputs():

    _w = (lambda a: (lambda t: t.to(torch.bfloat16) if t.is_floating_point() else t)(torch.as_tensor(a)))
    def _A_setup():
        B, S, D = 1, 2048, 512
        P = D
        Lambda_re = -0.5 * (lambda _x: torch.exp(torch.as_tensor(_x)))((lambda *s: torch.randn(*s, dtype=torch.bfloat16) * 0.4)(P))
        Lambda_im = (lambda *s: torch.randn(*s, dtype=torch.bfloat16) * 0.8)(P) * 1.0
        B_re = (lambda *s: torch.randn(*s, dtype=torch.bfloat16) * 0.4)(P, D) * (D ** -0.5)
        B_im = (lambda *s: torch.randn(*s, dtype=torch.bfloat16) * 0.4)(P, D) * (D ** -0.5)
        C_re = (lambda *s: torch.randn(*s, dtype=torch.bfloat16) * 0.4)(D, P) * (P ** -0.5)
        C_im = (lambda *s: torch.randn(*s, dtype=torch.bfloat16) * 0.4)(D, P) * (P ** -0.5)
        log_dt = (lambda *s: torch.randn(*s, dtype=torch.bfloat16) * 0.4)(P) * 0.3 - 2.0
        Dskip = (lambda *s: torch.randn(*s, dtype=torch.bfloat16) * 0.2)(D)
        return {
            "x": _w((lambda *s: torch.randn(*s, dtype=torch.bfloat16) * 0.05)(B, S, D)),
            "Lambda_re": _w(Lambda_re),
            "Lambda_im": _w(Lambda_im),
            "B_re": _w(B_re),
            "B_im": _w(B_im),
            "C_re": _w(C_re),
            "C_im": _w(C_im),
            "log_dt": _w(log_dt),
            "Dskip": _w(Dskip),
        }
    _A_in = _A_setup()

    def _B_setup():
        B, S, D, F = 1, 2048, 512, 1376
        return {
            "x": _w((lambda *s: torch.randn(*s, dtype=torch.bfloat16) * 0.05)(B, S, D)),
            "w1": _w((lambda *s: torch.randn(*s, dtype=torch.bfloat16) * 0.8)(D, F) * (D ** -0.5)),
            "b1": _w((lambda *s: torch.randn(*s, dtype=torch.bfloat16) * 0.2)(F)),
            "w2": _w((lambda *s: torch.randn(*s, dtype=torch.bfloat16) * 0.1)(F, D) * (F ** -0.5)),
        }
    _B_in = _B_setup()

    return {
        "A_x": _A_in["x"],
        "A_Lambda_re": _A_in["Lambda_re"],
        "A_Lambda_im": _A_in["Lambda_im"],
        "A_B_re": _A_in["B_re"],
        "A_B_im": _A_in["B_im"],
        "A_C_re": _A_in["C_re"],
        "A_C_im": _A_in["C_im"],
        "A_log_dt": _A_in["log_dt"],
        "A_Dskip": _A_in["Dskip"],
        "B_x": _B_in["x"],
        "B_w1": _B_in["w1"],
        "B_b1": _B_in["b1"],
        "B_w2": _B_in["w2"],
    }

def reference(A_x, A_Lambda_re, A_Lambda_im, A_B_re, A_B_im, A_C_re, A_C_im, A_log_dt, A_Dskip, B_x, B_w1, B_b1, B_w2):
    def _A_ref(x, Lambda_re, Lambda_im, B_re, B_im, C_re, C_im, log_dt, Dskip):
        Bsz, L, H = x.shape
        Lam = Lambda_re + 1j * Lambda_im
        Bmat = B_re + 1j * B_im
        Cmat = C_re + 1j * C_im
        dt = torch.exp(log_dt)
        Lam_bar = torch.exp(dt * Lam)
        B_bar = ((Lam_bar - 1.0) / Lam)[:, None] * Bmat
        Bu = torch.einsum("bld,pd->blp", x + 0j, B_bar)
        h = torch.zeros_like(Bu[:, 0, :])
        hs = []
        for t in range(L):
            h = Lam_bar[None, :] * h + Bu[:, t, :]
            hs.append(h)
        hseq = torch.stack(hs, 1)
        y = 2.0 * torch.einsum("blp,dp->bld", hseq, Cmat).real + x * Dskip[None, None, :]
        return y

    def _B_ref(x, w1, b1, w2):
        h = torch.einsum("bsd,df->bsf", x, w1) + b1
        sp = torch.log1p(torch.exp(-torch.abs(h))) + torch.where(h > 0, h, torch.zeros_like(h))
        act = h * torch.tanh(sp)
        return torch.einsum("bsf,fd->bsd", act, w2)

    x = A_x
    xn = _layernorm(x, axis=-1)
    s = _A_ref(xn, A_Lambda_re, A_Lambda_im, A_B_re, A_B_im, A_C_re, A_C_im, A_log_dt, A_Dskip)
    g = _silu(_B_ref(xn, B_w1, B_b1, B_w2))
    return x + s * g
```

```cpp
#include <cuda_runtime.h>
#include <cuda_bf16.h>
#include <cuda.h>
#include <stdint.h>
#include <stdio.h>
#include <type_traits>

template<int TA, int TB> __device__ __forceinline__ void wgmma_ss_n128(float (&d)[64], uint64_t da, uint64_t db, int scaleD){
  asm volatile("{\n.reg .pred p;\nsetp.ne.b32 p, %66, 0;\n"
  "wgmma.mma_async.sync.aligned.m64n128k16.f32.bf16.bf16 {%0, %1, %2, %3, %4, %5, %6, %7, %8, %9, %10, %11, %12, %13, %14, %15, %16, %17, %18, %19, %20, %21, %22, %23, %24, %25, %26, %27, %28, %29, %30, %31, %32, %33, %34, %35, %36, %37, %38, %39, %40, %41, %42, %43, %44, %45, %46, %47, %48, %49, %50, %51, %52, %53, %54, %55, %56, %57, %58, %59, %60, %61, %62, %63}, %64, %65, p, 1, 1, %67, %68;\n}\n"
  : "+f"(d[0]), "+f"(d[1]), "+f"(d[2]), "+f"(d[3]), "+f"(d[4]), "+f"(d[5]), "+f"(d[6]), "+f"(d[7]), "+f"(d[8]), "+f"(d[9]), "+f"(d[10]), "+f"(d[11]), "+f"(d[12]), "+f"(d[13]), "+f"(d[14]), "+f"(d[15]), "+f"(d[16]), "+f"(d[17]), "+f"(d[18]), "+f"(d[19]), "+f"(d[20]), "+f"(d[21]), "+f"(d[22]), "+f"(d[23]), "+f"(d[24]), "+f"(d[25]), "+f"(d[26]), "+f"(d[27]), "+f"(d[28]), "+f"(d[29]), "+f"(d[30]), "+f"(d[31]), "+f"(d[32]), "+f"(d[33]), "+f"(d[34]), "+f"(d[35]), "+f"(d[36]), "+f"(d[37]), "+f"(d[38]), "+f"(d[39]), "+f"(d[40]), "+f"(d[41]), "+f"(d[42]), "+f"(d[43]), "+f"(d[44]), "+f"(d[45]), "+f"(d[46]), "+f"(d[47]), "+f"(d[48]), "+f"(d[49]), "+f"(d[50]), "+f"(d[51]), "+f"(d[52]), "+f"(d[53]), "+f"(d[54]), "+f"(d[55]), "+f"(d[56]), "+f"(d[57]), "+f"(d[58]), "+f"(d[59]), "+f"(d[60]), "+f"(d[61]), "+f"(d[62]), "+f"(d[63])
  : "l"(da), "l"(db), "r"(scaleD), "n"(TA), "n"(TB));
}

template<int TA, int TB> __device__ __forceinline__ void wgmma_ss_n136(float (&d)[68], uint64_t da, uint64_t db, int scaleD){
  asm volatile("{\n.reg .pred p;\nsetp.ne.b32 p, %70, 0;\n"
  "wgmma.mma_async.sync.aligned.m64n136k16.f32.bf16.bf16 {%0, %1, %2, %3, %4, %5, %6, %7, %8, %9, %10, %11, %12, %13, %14, %15, %16, %17, %18, %19, %20, %21, %22, %23, %24, %25, %26, %27, %28, %29, %30, %31, %32, %33, %34, %35, %36, %37, %38, %39, %40, %41, %42, %43, %44, %45, %46, %47, %48, %49, %50, %51, %52, %53, %54, %55, %56, %57, %58, %59, %60, %61, %62, %63, %64, %65, %66, %67}, %68, %69, p, 1, 1, %71, %72;\n}\n"
  : "+f"(d[0]), "+f"(d[1]), "+f"(d[2]), "+f"(d[3]), "+f"(d[4]), "+f"(d[5]), "+f"(d[6]), "+f"(d[7]), "+f"(d[8]), "+f"(d[9]), "+f"(d[10]), "+f"(d[11]), "+f"(d[12]), "+f"(d[13]), "+f"(d[14]), "+f"(d[15]), "+f"(d[16]), "+f"(d[17]), "+f"(d[18]), "+f"(d[19]), "+f"(d[20]), "+f"(d[21]), "+f"(d[22]), "+f"(d[23]), "+f"(d[24]), "+f"(d[25]), "+f"(d[26]), "+f"(d[27]), "+f"(d[28]), "+f"(d[29]), "+f"(d[30]), "+f"(d[31]), "+f"(d[32]), "+f"(d[33]), "+f"(d[34]), "+f"(d[35]), "+f"(d[36]), "+f"(d[37]), "+f"(d[38]), "+f"(d[39]), "+f"(d[40]), "+f"(d[41]), "+f"(d[42]), "+f"(d[43]), "+f"(d[44]), "+f"(d[45]), "+f"(d[46]), "+f"(d[47]), "+f"(d[48]), "+f"(d[49]), "+f"(d[50]), "+f"(d[51]), "+f"(d[52]), "+f"(d[53]), "+f"(d[54]), "+f"(d[55]), "+f"(d[56]), "+f"(d[57]), "+f"(d[58]), "+f"(d[59]), "+f"(d[60]), "+f"(d[61]), "+f"(d[62]), "+f"(d[63]), "+f"(d[64]), "+f"(d[65]), "+f"(d[66]), "+f"(d[67])
  : "l"(da), "l"(db), "r"(scaleD), "n"(TA), "n"(TB));
}

template<int TB> __device__ __forceinline__ void wgmma_rs_n128(float (&d)[64], uint32_t a0, uint32_t a1, uint32_t a2, uint32_t a3, uint64_t db, int scaleD){
  asm volatile("{\n.reg .pred p;\nsetp.ne.b32 p, %69, 0;\n"
  "wgmma.mma_async.sync.aligned.m64n128k16.f32.bf16.bf16 {%0, %1, %2, %3, %4, %5, %6, %7, %8, %9, %10, %11, %12, %13, %14, %15, %16, %17, %18, %19, %20, %21, %22, %23, %24, %25, %26, %27, %28, %29, %30, %31, %32, %33, %34, %35, %36, %37, %38, %39, %40, %41, %42, %43, %44, %45, %46, %47, %48, %49, %50, %51, %52, %53, %54, %55, %56, %57, %58, %59, %60, %61, %62, %63}, {%64, %65, %66, %67}, %68, p, 1, 1, %70;\n}\n"
  : "+f"(d[0]), "+f"(d[1]), "+f"(d[2]), "+f"(d[3]), "+f"(d[4]), "+f"(d[5]), "+f"(d[6]), "+f"(d[7]), "+f"(d[8]), "+f"(d[9]), "+f"(d[10]), "+f"(d[11]), "+f"(d[12]), "+f"(d[13]), "+f"(d[14]), "+f"(d[15]), "+f"(d[16]), "+f"(d[17]), "+f"(d[18]), "+f"(d[19]), "+f"(d[20]), "+f"(d[21]), "+f"(d[22]), "+f"(d[23]), "+f"(d[24]), "+f"(d[25]), "+f"(d[26]), "+f"(d[27]), "+f"(d[28]), "+f"(d[29]), "+f"(d[30]), "+f"(d[31]), "+f"(d[32]), "+f"(d[33]), "+f"(d[34]), "+f"(d[35]), "+f"(d[36]), "+f"(d[37]), "+f"(d[38]), "+f"(d[39]), "+f"(d[40]), "+f"(d[41]), "+f"(d[42]), "+f"(d[43]), "+f"(d[44]), "+f"(d[45]), "+f"(d[46]), "+f"(d[47]), "+f"(d[48]), "+f"(d[49]), "+f"(d[50]), "+f"(d[51]), "+f"(d[52]), "+f"(d[53]), "+f"(d[54]), "+f"(d[55]), "+f"(d[56]), "+f"(d[57]), "+f"(d[58]), "+f"(d[59]), "+f"(d[60]), "+f"(d[61]), "+f"(d[62]), "+f"(d[63])
  : "r"(a0), "r"(a1), "r"(a2), "r"(a3), "l"(db), "r"(scaleD), "n"(TB));
}

__device__ __forceinline__ void wgmma_init_n128(float (&d)[64], uint64_t da, uint64_t db){
  asm volatile("{\n.reg .pred p;\nsetp.ne.b32 p, 0, 0;\n"
  "wgmma.mma_async.sync.aligned.m64n128k16.f32.bf16.bf16 {%0, %1, %2, %3, %4, %5, %6, %7, %8, %9, %10, %11, %12, %13, %14, %15, %16, %17, %18, %19, %20, %21, %22, %23, %24, %25, %26, %27, %28, %29, %30, %31, %32, %33, %34, %35, %36, %37, %38, %39, %40, %41, %42, %43, %44, %45, %46, %47, %48, %49, %50, %51, %52, %53, %54, %55, %56, %57, %58, %59, %60, %61, %62, %63}, %64, %65, p, 1, 1, 0, 0;\n}\n"
  : "=f"(d[0]), "=f"(d[1]), "=f"(d[2]), "=f"(d[3]), "=f"(d[4]), "=f"(d[5]), "=f"(d[6]), "=f"(d[7]), "=f"(d[8]), "=f"(d[9]), "=f"(d[10]), "=f"(d[11]), "=f"(d[12]), "=f"(d[13]), "=f"(d[14]), "=f"(d[15]), "=f"(d[16]), "=f"(d[17]), "=f"(d[18]), "=f"(d[19]), "=f"(d[20]), "=f"(d[21]), "=f"(d[22]), "=f"(d[23]), "=f"(d[24]), "=f"(d[25]), "=f"(d[26]), "=f"(d[27]), "=f"(d[28]), "=f"(d[29]), "=f"(d[30]), "=f"(d[31]), "=f"(d[32]), "=f"(d[33]), "=f"(d[34]), "=f"(d[35]), "=f"(d[36]), "=f"(d[37]), "=f"(d[38]), "=f"(d[39]), "=f"(d[40]), "=f"(d[41]), "=f"(d[42]), "=f"(d[43]), "=f"(d[44]), "=f"(d[45]), "=f"(d[46]), "=f"(d[47]), "=f"(d[48]), "=f"(d[49]), "=f"(d[50]), "=f"(d[51]), "=f"(d[52]), "=f"(d[53]), "=f"(d[54]), "=f"(d[55]), "=f"(d[56]), "=f"(d[57]), "=f"(d[58]), "=f"(d[59]), "=f"(d[60]), "=f"(d[61]), "=f"(d[62]), "=f"(d[63])
  : "l"(da), "l"(db));
}

#define BOUNDED_WAIT
constexpr int kL = 2048, kD = 512, kF = 1376;
constexpr int kTiles = 16;
constexpr int kNCH = 38;
constexpr uint32_t kStage = 17 * 1024;
constexpr uint32_t kOffW = 8 * kStage;
constexpr uint32_t kOffXo = kOffW + 4 * 16384;
constexpr uint32_t kOffLN = kOffXo + 16384;
constexpr uint32_t kOffCst = kOffLN + 1024;
constexpr uint32_t kOffFix = kOffCst + 4096;
constexpr uint32_t kOffFixA = kOffFix + 2048;
constexpr uint32_t kOffScl = kOffFixA + 2048;
constexpr uint32_t kOffBar = kOffScl + 640;
constexpr uint32_t kBarFullX = 0, kBarFullA = 8, kBarXo = 28, kBarXr = 29, kBarRaw = 32, kBarFull2 = 72, kBarEmpty = 112,
                   kBarEmpty2 = 120, kBarTurn = 128, kBarSpare = 134, kBarRetry = 136, kBarF1Go = 140, kBarStats = 141;
constexpr uint32_t kBarXn = 142, kBarDone = 136;
constexpr uint32_t kOffProf = kOffBar + 1152;
constexpr uint32_t kSmemBytes = kOffProf + 256;

#define TRACE 0
#define ARRIVE_K 5
#define SLEEP1 600
#define SLEEP2 200
#define SLEEP3 100
#define SLEEP4 0
#define BSUM_WAIT 3
#define F1_GO 2
#define HOLD0 600
#define HOLD1 320
#define GATE_X 2
#define GATE_D 310
#define TRMASK 15
#define GATE_Y 2
#define NORM_WAIT -1
#define NORM_PACE 0
#define NOPACE 0
#define NORM_WG 1
#define F2_GO -1
#define NOPOLL 0
#define NOROT 0
#define VISSUE 0
#define WGMAP 0x32104
#define WORDER 0x6420
#define PIPE_POLL 0
#define S1_YIELD 122
#define SP_S 0
#define SP_F 0
#define SP_NS 20
#define PF2 3
#define MAP 1
#define S0_YIELD 0
#define EV0 22
#define EV1 27
#define DUMMY 1
#define TMA2 1
#define NPIECE 7
#define PORDER(i) ((((i) & 3) << 1) | ((i) >> 2))
#define QTMA 3
#define QISS 3
#define P2_UNROLL 2
#define F0_LEAN 0
#define PADN 0
#define MISH_IT 1
#define SKIP_AT 31
#define LAUNDER 0
#define MFENCE 7
#define SFENCE 0
#define PF_I 7
#define SLEEP5 100
#define LOADS_LATE 0
#define MSPLIT 0
#define NORM_EV 0
#define START_GAP 0
#define S0_FREE 1
#define BPF -1
#define XTRA 5
#define WARM 2
#define F0V 1
#define PF_MODE 1
#define PF_WAIT 3
constexpr uint32_t kOffXr = SKIP_AT == 16 ? kOffXo : 6 * kStage;
constexpr int kSpinLimit = 200000;
constexpr float kLog2e = 1.4426950408889634f, kLn2 = 0.6931471805599453f;

__device__ uint4 g_hid[kTiles * (kNCH + 2) * 1024];
__device__ float2 g_agg[kTiles * 8 * 64];
__device__ float2 g_stat[kL];
__device__ uint32_t g_wsum[1024];
__device__ uint32_t g_epoch[128 * 32];
#define RETRY(i)
#define TQ(k, c)
#define TR(k, c)
#define PROFX(i)
#define PROF(i)
#define PROFW(i)

struct Params {
  uint4* hid;
  float2 *agg, *stat;
  float* out;
  uint32_t *epoch, *wsum;
  const __nv_bfloat16 *lam_re, *lam_im, *log_dt, *dskip, *b1, *w1, *w2, *c_re, *c_im, *b_re, *b_im;
  int swapB, swapC;
};

__device__ __forceinline__ void mbar_init(uint32_t a, uint32_t c) {
  asm volatile("mbarrier.init.shared::cta.b64 [%0], %1;" ::"r"(a), "r"(c) : "memory");
}
__device__ __forceinline__ void mbar_expect(uint32_t a, uint32_t b) {
  asm volatile("mbarrier.arrive.expect_tx.shared::cta.b64 _, [%0], %1;" ::"r"(a), "r"(b) : "memory");
}
__device__ __forceinline__ void mbar_arrive(uint32_t a) {
  asm volatile("mbarrier.arrive.shared::cta.b64 _, [%0];" ::"r"(a) : "memory");
}
__device__ __forceinline__ void mbar_arrive_elect(uint32_t a) {
  asm volatile("{\n.reg .pred P;\nelect.sync _|P, 0xffffffff;\n@P mbarrier.arrive.shared::cta.b64 _, [%0];\n}" ::"r"(a) : "memory");
}
__device__ __forceinline__ void mbar_arrive_elect2(uint32_t a) {
  asm volatile("{\n.reg .pred P;\nelect.sync _|P, 0xffffffff;\n@P mbarrier.arrive.shared::cta.b64 _, [%0];\n@P mbarrier.arrive.shared::cta.b64 _, [%0+8];\n}" ::"r"(a) : "memory");
}
__device__ __forceinline__ void mbar_wait(uint32_t a, uint32_t ph) {
  asm volatile(
      "{\n.reg .pred P;\n.reg .u32 c;\nmov.u32 c, 0;\n"
      "LAB_WAIT:\n"
      "mbarrier.try_wait.parity.shared::cta.b64 P, [%0], %1;\n"
      "@P bra LAB_DONE;\n"
      "add.u32 c, c, 1;\nsetp.lt.u32 P, c, 400000;\n@P bra LAB_WAIT;\ntrap;\n"
      "LAB_DONE:\n}" ::"r"(a), "r"(ph) : "memory");
}
__device__ __forceinline__ void mbar_wait2(uint32_t a, uint32_t b) {
  mbar_wait(a, 0);
  mbar_wait(b, 0);
}
__device__ __forceinline__ uint32_t mbar_test(uint32_t a) {
  uint32_t r;
  asm volatile("{\n.reg .pred P;\nmbarrier.test_wait.parity.shared::cta.b64 P, [%1], 0;\nselp.u32 %0, 1, 0, P;\n}" : "=r"(r) : "r"(a) : "memory");
  return r;
}
__device__ __forceinline__ bool elect_one() {
  uint32_t p;
  asm volatile("{\n.reg .pred P;\nelect.sync _|P, 0xffffffff;\nselp.u32 %0, 1, 0, P;\n}" : "=r"(p));
  return p;
}
__device__ __forceinline__ void tma2d(uint32_t dst, const CUtensorMap* tm, uint32_t bar, int c0, int c1) {
  asm volatile("cp.async.bulk.tensor.2d.shared::cluster.global.mbarrier::complete_tx::bytes [%0], [%1, {%3, %4}], [%2];"
               ::"r"(dst), "l"(tm), "r"(bar), "r"(c0), "r"(c1) : "memory");
}
__device__ __forceinline__ void tma3d(uint32_t dst, const CUtensorMap* tm, uint32_t bar, int c0, int c1, int c2) {
  asm volatile("cp.async.bulk.tensor.3d.shared::cluster.global.mbarrier::complete_tx::bytes [%0], [%1, {%3, %4, %5}], [%2];"
               ::"r"(dst), "l"(tm), "r"(bar), "r"(c0), "r"(c1), "r"(c2) : "memory");
}
__device__ __forceinline__ void tma5d(uint32_t dst, const CUtensorMap* tm, uint32_t bar, int c0, int c3, int c4) {
  asm volatile("cp.async.bulk.tensor.5d.shared::cluster.global.mbarrier::complete_tx::bytes [%0], [%1, {%3, %4, %4, %5, %6}], [%2];"
               ::"r"(dst), "l"(tm), "r"(bar), "r"(c0), "r"(0), "r"(c3), "r"(c4) : "memory");
}
__device__ __forceinline__ void stg128(uint4* a, const uint32_t (&v)[4]) {
  asm volatile("st.global.v4.u32 [%0], {%1,%2,%3,%4};" ::"l"(a), "r"(v[0]), "r"(v[1]), "r"(v[2]), "r"(v[3]) : "memory");
}
__device__ __forceinline__ void sts128(uint32_t a, float x, float y, float z, float w) {
  asm volatile("st.shared.v4.f32 [%0], {%1,%2,%3,%4};" ::"r"(a), "f"(x), "f"(y), "f"(z), "f"(w) : "memory");
}
__device__ __forceinline__ uint64_t mkdesc(uint32_t addr, uint32_t lbo, uint32_t sbo, uint64_t swz) {
  return (uint64_t)((addr & 0x3FFFF) >> 4) | ((uint64_t)(lbo >> 4) << 16) | ((uint64_t)(sbo >> 4) << 32) | (swz << 62);
}
__device__ __forceinline__ uint64_t desc2(uint32_t lo, uint32_t hi) {
  uint64_t d;
  asm("mov.b64 %0, {%1, %2};" : "=l"(d) : "r"(lo), "r"(hi));
  return d;
}
constexpr uint32_t kHi128 = 0x40000040u, kHiH = 0x80000080u;
#define WG_FENCE() asm volatile("wgmma.fence.sync.aligned;" ::: "memory")
#define WG_COMMIT() asm volatile("wgmma.commit_group.sync.aligned;" ::: "memory")
#define WG_WAIT(n) asm volatile("wgmma.wait_group.sync.aligned " #n ";" ::: "memory")
template <int N>
__device__ __forceinline__ void reg_fence(float (&d)[N]) {
#pragma unroll
  for (int i = 0; i < N; i++) asm volatile("" : "+f"(d[i])::"memory");
}
template <int N>
__device__ __forceinline__ void reg_define(float (&d)[N]) {
#pragma unroll
  for (int i = 0; i < N; i++) asm volatile("mov.b32 %0, 0;" : "=f"(d[i]));
}
__device__ __forceinline__ uint32_t pack_bf16(float lo, float hi) {
  uint32_t r;
  asm("cvt.rn.bf16x2.f32 %0, %1, %2;" : "=r"(r) : "f"(hi), "f"(lo));
  return r;
}
__device__ __forceinline__ float ex2f(float x) { float r; asm("ex2.approx.ftz.f32 %0, %1;" : "=f"(r) : "f"(x)); return r; }
__device__ __forceinline__ float rcpf(float x) { float r; asm("rcp.approx.ftz.f32 %0, %1;" : "=f"(r) : "f"(x)); return r; }
__device__ __forceinline__ float tanhf_(float x) { float r; asm("tanh.approx.f32 %0, %1;" : "=f"(r) : "f"(x)); return r; }
__device__ __forceinline__ float4 lds128(uint32_t a) {
  float4 v;
  asm volatile("ld.shared.v4.f32 {%0,%1,%2,%3}, [%4];" : "=f"(v.x), "=f"(v.y), "=f"(v.z), "=f"(v.w) : "r"(a) : "memory");
  return v;
}
__device__ __forceinline__ float bf_lo(uint32_t v) { return __uint_as_float(v << 16); }
__device__ __forceinline__ float bf_hi(uint32_t v) { return __uint_as_float(v & 0xffff0000u); }
__device__ __forceinline__ float2 cmul(float2 a, float2 b) { return make_float2(a.x * b.x - a.y * b.y, a.x * b.y + a.y * b.x); }
__device__ __forceinline__ float2 cfma(float2 a, float2 b, float2 c) {
  return make_float2(fmaf(a.x, b.x, fmaf(-a.y, b.y, c.x)), fmaf(a.x, b.y, fmaf(a.y, b.x, c.y)));
}
__device__ __forceinline__ void ln_fixup(float (&acc)[68], float biasA, float biasB, int q, uint32_t fix, uint32_t ready, uint32_t sb, int pf) {
  float va = acc[64], vb = acc[66];
  const uint32_t hi = pack_bf16(va, vb);
  if (q == 1) { va -= bf_lo(hi); vb -= bf_hi(hi); }
  if (q >= 2) { va = biasA; vb = biasB; }
  const uint32_t a0 = pack_bf16(va, va), a1 = pack_bf16(vb, vb);
  mbar_wait(ready, 0);
  PROF(pf);
  WG_FENCE();
  wgmma_rs_n128<0>(reinterpret_cast<float(&)[64]>(acc), a0, a1, a0, a1, mkdesc(fix, 0, 128, 0), 1);
  WG_COMMIT();
  WG_WAIT(0);
  reg_fence(acc);
}
__device__ __forceinline__ uint32_t load_epoch(const uint32_t* a) {
  uint32_t e;
  asm volatile("ld.relaxed.gpu.global.u32 %0, [%1];" : "=r"(e) : "l"(a) : "memory");
  return e + 1;
}
__device__ __forceinline__ void l2_prefetch(const void* a, uint32_t bytes) {
  asm volatile("cp.async.bulk.prefetch.L2.global [%0], %1;" ::"l"(a), "r"(bytes) : "memory");
}

__global__ void __launch_bounds__(640, 1)
s5_mish_fused_kernel(const Params p, const __grid_constant__ CUtensorMap tmX, const __grid_constant__ CUtensorMap tmW1,
                     const __grid_constant__ CUtensorMap tmB, const __grid_constant__ CUtensorMap tmC,
                     const __grid_constant__ CUtensorMap tmW2, const __grid_constant__ CUtensorMap tmOut,
                     const __grid_constant__ CUtensorMap tmXo) {
  extern __shared__ __align__(1024) uint8_t smem_raw[];
  const uint32_t sb = (uint32_t)__cvta_generic_to_shared(smem_raw);
  const uint32_t bar0 = sb + kOffBar;
  int tid = threadIdx.x;
  if (LAUNDER) asm volatile("and.b32 %0, %0, 1023;" : "+r"(tid));
  const int warp = __shfl_sync(0xffffffffu, tid >> 5, 0);
  const int lane = tid & 31;
  const int bx = MAP == 0 ? blockIdx.x : MAP == 1 ? (blockIdx.x & 0x63) | ((blockIdx.x & 0xC) << 1) | ((blockIdx.x & 0x10) >> 2) : (blockIdx.x & 0x70) | ((blockIdx.x & 1) << 3) | ((blockIdx.x & 0xE) >> 1);
  const int tile = bx >> 3, slice = bx & 7;
  constexpr int nP1 = 20;
  const uint32_t sb16 = sb >> 4;

  if (warp == 16) {
    const bool el = elect_one();
    if (el) {
      mbar_init(bar0, 1);
      mbar_init(bar0 + kBarFullA * 8, 1);
      mbar_expect(bar0, 16384);
      mbar_expect(bar0 + kBarFullA * 8, 16384);
      asm volatile("fence.mbarrier_init.release.cluster;" ::: "memory");
      tma5d(sb, &tmX, bar0, 0, 0, tile);
      tma2d(sb + kOffW, &tmW1, bar0 + kBarFullA * 8, slice * 64, 0);
      PROFX(29);
#pragma unroll
      for (int i = 1; i < 12; i++) if (i != 8) mbar_init(bar0 + i * 8, 1);
    }
    __syncwarp();
    if (lane < 12 && (lane & 7)) mbar_expect(bar0 + lane * 8, 16384);
    asm volatile("bar.arrive 2, 224;\nbar.arrive 1, 608;" ::: "memory");
    if (START_GAP) { uint32_t a, b; asm volatile("mov.u32 %0, %%clock;" : "=r"(a)); do { asm volatile("mov.u32 %0, %%clock;" : "=r"(b)); } while (b - a < START_GAP); }
    if (el) {
      asm volatile("fence.mbarrier_init.release.cluster;" ::: "memory");
#pragma unroll
      for (int i = 1; i < 8; i++) {
        tma5d(sb + i * kStage, &tmX, bar0 + i * 8, i * 64, 0, tile);
        if (!(i & 1)) tma2d(sb + kOffW + (XTRA && i == 6 ? 8 : i) * 8192, &tmW1, bar0 + kBarFullA * 8 + i * 4, slice * 64, i * 64);
      }
      PROFX(30);
    }
  } else if (warp >= 18) {
#pragma unroll
    for (int i = 0; i < 8; i++)
      asm volatile("st.shared.v4.u32 [%0], {%1,%1,%1,%1};" ::"r"(sb + i * kStage + 16384 + (tid & 63) * 16), "r"(0x3F803F80u) : "memory");
    asm volatile("fence.proxy.async.shared::cta;" ::: "memory");
    asm volatile("bar.arrive 2, 224;\nbar.arrive 1, 608;" ::: "memory");
  }

  if (warp >= 16) {
    asm volatile("setmaxnreg.dec.sync.aligned.u32 32;");
    asm volatile("bar.sync 0, 640;" ::: "memory");
    const int s = warp & 3;
    const bool el = elect_one();
    uint32_t epoch;
    asm volatile("ld.relaxed.gpu.global.u32 %0, [%1];" : "=r"(epoch) : "l"(p.epoch + blockIdx.x * 32 + lane) : "memory");
    if (BPF >= 0 && s == 3) {
      mbar_wait(bar0 + (kBarFullX + BPF) * 8, 0);
      if (el) l2_prefetch((const char*)((blockIdx.x & 1) ? p.b_re : p.b_im) + (blockIdx.x >> 1) * 4096, 4096);
    }
    const uint32_t dst = sb + kOffW + s * 16384, eb = bar0 + (kBarEmpty + 2 * s) * 8;
    uint32_t ph = XTRA && s == 3, rph = 0;
    if (XTRA && s == 3) mbar_wait(bar0 + (kBarFullX + XTRA) * 8, 0);
#pragma unroll 1
    for (int i = 4 + s; i < nP1; i += 4, ph ^= 1) {
      mbar_wait(eb, ph);
      if (el) {
        const uint32_t bar = bar0 + (kBarFullA + i) * 8;
        if (i < 12) tma5d(dst, &tmB, bar, 0, (i & 8) * 4 + slice * 4, s * 2);
        else tma2d(dst, &tmW1, bar, ((i < 16 ? 8 : 16) + slice) * 64, s * 128);
        if (i == PF_I) l2_prefetch((const char*)p.w1 + blockIdx.x * 11008, 11008);
        if (i == 8 + s) {
          if (s == 0) { if (PF2 & 1) l2_prefetch((const char*)p.w2 + blockIdx.x * 11008, 11008); }
          else if (s == 3) {
            tma5d(sb + kOffXo, &tmXo, bar0 + kBarXo * 8, slice * 64, 0, tile);
            asm volatile("prefetch.tensormap [%0];" ::"l"(&tmOut) : "memory");
          }
          else {
            if (PF2 & 2) l2_prefetch((const char*)(s == 1 ? p.c_re : p.c_im) + blockIdx.x * 4096, 4096);
            asm volatile("prefetch.tensormap [%0];" ::"l"(s == 1 ? &tmC : &tmW2) : "memory");
          }
        }
      }
    }
    const char* hid = (const char*)(p.hid + tile * kNCH * 1024);
    if (s == 0) {
#pragma unroll 1
      for (int c = 0; c < kNCH; c++) {
        asm volatile(
            "{\n.reg .pred P, E;\nelect.sync _|E, 0xffffffff;\n"
            "LAB_WAIT:\n"
            "mbarrier.try_wait.parity.shared::cta.b64 P, [%0], %1;\n"
            "@!P bra LAB_WAIT;\n"
            "@E cp.async.bulk.shared::cluster.global.mbarrier::complete_tx::bytes [%2], [%3], 16384, [%4];\n}"
            ::"r"(bar0 + (kBarEmpty2 + (c & 7)) * 8), "r"((c >> 3) & 1), "r"(sb + (c & 7) * kStage), "l"(hid + c * 16384),
              "r"(bar0 + (kBarRaw + c) * 8) : "memory");
        TR(0, c);
        if (!(c & 7)) PROFW(20 + (c >> 3));
      }
      if (SKIP_AT != 16) mbar_wait(bar0 + (kBarEmpty2 + 6) * 8, 0);
      if (el) tma5d(sb + kOffXr, &tmXo, bar0 + kBarXr * 8, slice * 64, 0, tile);
    } else if (s == 1) {
      int c = 0;
      auto run = [&](int n, const CUtensorMap* tm, int k0, int sc) {
#pragma unroll 1
        for (int k = k0; k < k0 + n; k++, c++)
          asm volatile(
              "{\n.reg .pred P, E;\nelect.sync _|E, 0xffffffff;\n"
              "LAB_WAIT:\n"
              "mbarrier.try_wait.parity.shared::cta.b64 P, [%0], %1;\n"
              "@!P bra LAB_WAIT;\n"
              "@E cp.async.bulk.tensor.3d.shared::cluster.global.mbarrier::complete_tx::bytes [%2], [%3, {%5, %6, %7}], [%4];\n}"
              ::"r"(bar0 + (kBarEmpty2 + (c & 7)) * 8), "r"((c >> 3) & 1), "r"(sb + kOffW + (c & 7) * 8192), "l"(tm),
                "r"(bar0 + (kBarRaw + c) * 8), "r"(sc ? (k & 14) * 32 : slice * 64), "r"(sc ? slice * 64 : k * 64), "r"(k & sc) : "memory");
      };
#pragma unroll 1
      for (int r = 0; r < 2; r++) {
        run(r ? 14 : 8, &tmW2, r * 8, 0);
        run(8, &tmC, r * 8, 1);
      }
    } else {
      const uint32_t la = sb + lane * 128 + (lane & 3) * 32 + (lane & 16) + (lane & 4);
      int it = 0, missed = -1;
#pragma unroll 1
      for (int d = s - 2; d < kNCH;) {
        uint32_t ok;
        asm volatile(
            "{\n.reg .pred P, E;\n.reg .b32 a, b, c, d;\n"
            "elect.sync _|E, 0xffffffff;\n"
            "LAB_WAIT:\n"
            "mbarrier.try_wait.parity.shared::cta.b64 P, [%3], 0;\n"
            "@!P bra LAB_WAIT;\n"
            "ld.shared.u32 a, [%1];\nld.shared.u32 b, [%1+4096];\nld.shared.u32 c, [%1+8192];\nld.shared.u32 d, [%1+12288];\n"
            "lop3.b32 a, a, b, %2, 0x42;\nlop3.b32 c, c, d, %2, 0x42;\nlop3.b32 a, a, c, 1, 0x80;\n"
            "setp.ne.u32 P, a, 0;\nvote.sync.all.pred P, P, 0xffffffff;\nand.pred E, E, P;\n"
            "@E mbarrier.arrive.shared::cta.b64 _, [%3+%4];\nselp.u32 %0, 1, 0, P;\n}"
            : "=r"(ok) : "r"(la + (d & 7) * kStage), "r"(epoch), "r"(bar0 + (kBarRaw + d) * 8), "n"((kBarFull2 - kBarRaw) * 8) : "memory");
        if (ok) {
          TR(2, d);
          if (!(d & 7) && d < 24) PROFW(15 + (d >> 3));
          d += 2;
          continue;
        }
        PROFW(44 + (d >> 3));
        RETRY(d < 8 ? 0 : d < 16 ? 2 : d < 24 ? 1 : d < 30 ? 3 : 4);
        if (d == missed) do {
          __nanosleep(SLEEP3);
          asm volatile("ld.relaxed.gpu.global.u32 %0, [%1];" : "=r"(ok)
                       : "l"(hid + d * 16384 + (lane >> 2) * 2048 + (lane & 4) * 4 + 1540 + (lane & 3) * 160) : "memory");
        } while (__any_sync(0xffffffffu, !((ok ^ epoch) & 1)) && ++it < kSpinLimit);
        missed = d;
        const uint32_t rb = bar0 + (kBarRetry + s) * 8;
        if (el) {
          mbar_expect(rb, 16384);
          asm volatile("cp.async.bulk.shared::cluster.global.mbarrier::complete_tx::bytes [%0], [%1], 16384, [%2];"
                       ::"r"(sb + (d & 7) * kStage), "l"(hid + d * 16384), "r"(rb) : "memory");
        }
        mbar_wait(rb, rph);
        rph ^= 1;
        if (++it >= kSpinLimit) {
          mbar_arrive_elect(bar0 + (kBarFull2 + d) * 8);
          d += 2;
        }
      }
    }
  } else {
    const int wgi = warp >> 2, w = warp & 3, g = lane >> 2, q = lane & 3;
    uint32_t epoch, bq, r_lr, r_li, r_dt;
    auto small_loads = [&]() {
      const int f = min(((q & 2) ? 16 : (wgi & 1) * 8) * 64 + slice * 64 + w * 16 + g + (q & 1) * 8, kF - 1);
      asm volatile("ld.global.u16 %0, [%1];" : "=r"(bq) : "l"(wgi < 2 ? p.dskip + slice * 64 + w * 16 + g + (q & 1) * 8 : p.b1 + f) : "memory");
      asm volatile("ld.relaxed.gpu.global.u32 %0, [%1];" : "=r"(epoch) : "l"(p.epoch + blockIdx.x * 32 + lane) : "memory");
    };
    if (wgi == 2) {
      if (elect_one()) {
#pragma unroll
        for (int i = 0; i < 4; i++) mbar_init(bar0 + (112 + w * 4 + i) * 8, 4);
        mbar_init(bar0 + (128 + w * 4) * 8, 4);
        mbar_init(bar0 + (129 + w * 4) * 8, w == 1 ? 10 : 4);
        mbar_init(bar0 + (130 + w * 4) * 8, w == 1 ? 1024 : w == 2 ? 1 : 4);
        mbar_init(bar0 + (131 + w * 4) * 8, w == 1 ? 1024 : w == 2 ? 1 : 4);
      }
      __syncwarp();
      asm volatile("bar.arrive 0, 640;\nbar.arrive 1, 608;" ::: "memory");
      epoch = bq = r_lr = r_li = r_dt = 0;
    } else {
      small_loads();
      const int c = (w & 1) * 256 + slice * 32 + lane;
      asm volatile("ld.global.nc.u16 %0, [%1];" : "=r"(r_lr) : "l"(p.lam_re + c));
      asm volatile("ld.global.nc.u16 %0, [%1];" : "=r"(r_li) : "l"(p.lam_im + c));
      asm volatile("ld.global.nc.u16 %0, [%1];" : "=r"(r_dt) : "l"(p.log_dt + c));
      const int w12 = warp < 8 ? warp : warp - 4, i = 12 + w12 + 12 * lane;
      if (elect_one()) {
#pragma unroll
        for (int k = 0; k < 8; k++) mbar_init(bar0 + (12 + w12 + 12 * k) * 8, 1);
        if (w12 < 4) mbar_init(bar0 + (108 + w12) * 8, 1);
      }
      __syncwarp();
      if (i < (int)kBarFull2) mbar_expect(bar0 + i * 8, i < (int)kBarRaw ? 16384 : 24576);
      asm volatile("bar.arrive 0, 640;\nbar.sync 1, 608;" ::: "memory");
    }
    if (warp == 0) PROF(51);

    if (wgi & 1) {
      const uint32_t tag = ~epoch & 1;
      const int t2 = (tid & 127) + (wgi >> 1) * 128;
      float2* stat = p.stat + bx * 16 + (t2 >> 4);
      uint32_t* wsum = p.wsum + blockIdx.x * 8 + w * 2 + (lane >> 4);
      if ((lane & 15) == 0) {
        asm volatile("st.relaxed.gpu.global.v2.u32 [%0], {%1,%1};" ::"l"(stat), "r"(tag ^ 1) : "memory");
        if (wgi == 3) asm volatile("st.relaxed.gpu.global.u32 [%0], %1;" ::"l"(wsum), "r"(tag ^ 1) : "memory");
      }
      float s = 0.f, qq = 0.f;
      auto chunk = [&](int k) {
        mbar_wait(bar0 + (kBarFullX + k) * 8, 0);
        uint32_t v0, v1;
        asm volatile("ld.shared.v2.u32 {%0,%1}, [%2];" : "=r"(v0), "=r"(v1) : "r"(sb + k * kStage + slice * 2048 + t2 * 8) : "memory");
        const float a = bf_lo(v0), b = bf_hi(v0), c = bf_lo(v1), d = bf_hi(v1);
        s += (a + b) + (c + d);
        qq = fmaf(a, a, fmaf(b, b, fmaf(c, c, fmaf(d, d, qq))));
      };
#pragma unroll 1
      for (int k = 0; k <= BSUM_WAIT; k++) chunk(k);
      uint4 bv[4];
      if (wgi == 3) {
        const uint4* brow = (const uint4*)(blockIdx.x < 64 ? p.b_re : p.b_im) + ((blockIdx.x & 63) * 8 + w * 2 + (lane >> 4)) * 64 + (lane & 15);
#pragma unroll
        for (int i = 0; i < 4; i++)
          asm volatile("ld.global.nc.v4.u32 {%0,%1,%2,%3}, [%4];" : "=r"(bv[i].x), "=r"(bv[i].y), "=r"(bv[i].z), "=r"(bv[i].w) : "l"(brow + 16 * i) : "memory");
      }
#pragma unroll 1
      for (int k = BSUM_WAIT + 1; k < 8; k++) chunk(k);
#pragma unroll
      for (int o = 1; o < 16; o *= 2) {
        s += __shfl_xor_sync(0xffffffffu, s, o);
        qq += __shfl_xor_sync(0xffffffffu, qq, o);
      }
      const float mu = s * (1.f / kD);
      const float var = fmaxf(fmaf(-mu, mu, qq * (1.f / kD)), 0.f);
      if ((lane & 15) == 0)
        asm volatile("st.relaxed.gpu.global.v2.u32 [%0], {%1,%2};" ::"l"(stat),
                     "r"((__float_as_uint(-mu) & ~1u) | tag), "r"((__float_as_uint(var + 1e-5f) & ~1u) | tag) : "memory");
      if (warp == 4) PROF(50);
      const int n = tid & 127;
      uint32_t v0, v1;
      int it = 0;
      if (wgi == 3) {
        s = 0.f;
#pragma unroll
        for (int i = 0; i < 4; i++)
          s += ((bf_lo(bv[i].x) + bf_hi(bv[i].x)) + (bf_lo(bv[i].y) + bf_hi(bv[i].y))) + ((bf_lo(bv[i].z) + bf_hi(bv[i].z)) + (bf_lo(bv[i].w) + bf_hi(bv[i].w)));
#pragma unroll
        for (int o = 1; o < 16; o *= 2) s += __shfl_xor_sync(0xffffffffu, s, o);
        if ((lane & 15) == 0) asm volatile("st.relaxed.gpu.global.u32 [%0], %1;" ::"l"(wsum), "r"((__float_as_uint(s) & ~1u) | tag) : "memory");
        const int r = n & 63;
        do {
          __nanosleep(SLEEP5);
          asm volatile("ld.relaxed.gpu.global.u32 %0, [%1];" : "=r"(v0)
                       : "l"(p.wsum + (((r >> 3) & 1) ^ p.swapB) * 512 + (n >> 6) * 256 + slice * 32 + (r >> 4) * 8 + (r & 7)) : "memory");
        } while (__any_sync(0xffffffffu, (v0 ^ tag) & 1) && ++it < kSpinLimit);
        const float ws = __uint_as_float(v0);
        const uint32_t w1 = pack_bf16(ws, ws);
        const float lo = ws - bf_hi(w1);
        asm volatile("st.shared.v4.u32 [%0], {%1,%2,%3,%3};" ::"r"(sb + kOffFixA + n * 16), "r"(w1), "r"(pack_bf16(lo, lo)), "r"(0) : "memory");
      } else {
        const int t = ((n >> 1) & 3) * 32 + (n >> 3) * 2 + (n & 1);
        do {
          asm volatile("ld.relaxed.gpu.global.v2.u32 {%0,%1}, [%2];" : "=r"(v0), "=r"(v1) : "l"(p.stat + tile * 128 + n) : "memory");
        } while (__any_sync(0xffffffffu, ((v0 ^ tag) | (v1 ^ tag)) & 1) && ++it < kSpinLimit);
        const float nmu = __uint_as_float(v0), rstd = rsqrtf(__uint_as_float(v1)), sig = __uint_as_float(v1) * rstd;
        const float hm = 0.5f * nmu, hs = 0.5f * sig;
        const uint32_t hi = pack_bf16(hm, hs);
        const uint32_t m12 = pack_bf16(hm, hm - bf_lo(hi)), s12 = pack_bf16(hs, hs - bf_hi(hi));
        asm volatile("st.shared.v4.u32 [%0], {%1,%1,%2,%3};" ::"r"(sb + kOffFix + n * 16), "r"(m12), "r"(s12), "r"(0) : "memory");
        asm volatile("st.shared.v2.f32 [%0], {%1,%2};" ::"r"(sb + kOffLN + t * 8), "f"(rstd), "f"(nmu * rstd) : "memory");
        asm volatile("st.shared.f32 [%0], %1;" ::"r"(sb + kOffScl + t * 4 + (t >> 5) * 16), "f"(rstd * kLog2e) : "memory");
      }
      asm volatile("fence.proxy.async.shared::cta;" ::: "memory");
      __syncwarp();
      if (lane <= (wgi == 1)) mbar_arrive(bar0 + (lane ? kBarStats : kBarTurn + 5) * 8);
      PROF(wgi == 1 ? 8 : 40);
    }

    if (wgi >= 2) {
      float acc[68];
#pragma unroll 1
      for (int b = wgi - 2; b < 3; b += 2) {
        const int fb = b * 8 + slice;
        uint32_t ra = bar0 + kBarSpare * 8;
        reg_define(acc);
        if (b == 0) {
          asm volatile("bar.sync 2, 224;" ::: "memory");
          if (WARM) {
            WG_FENCE();
#pragma unroll
            for (int i = 0; i < WARM; i++)
              wgmma_ss_n136<0, 0>(acc, desc2(sb16 + 1024, 0), desc2(sb16 + 1024, 0), 1);
            WG_COMMIT();
            WG_WAIT(0);
          }
          PROF(28);
#pragma unroll 1
          for (int k = 0; k < 4; k++) {
            const uint64_t da = desc2(sb16 + (kOffW >> 4) + (k == 3 ? 4 : k) * 1024 + (512u << 16), kHi128);
            const uint64_t db = desc2(sb16 + k * (kStage >> 3) + (1u << 16), kHi128);
            mbar_wait2(bar0 + (kBarFullA + k) * 8, bar0 + (kBarFullX + 2 * k) * 8);
            if (k == 0) PROF(2);
            WG_FENCE();
#pragma unroll
            for (int kk = 0; kk < 4; kk++) wgmma_ss_n136<1, 0>(acc, da + kk * 128, db + kk * 2, !WARM || (k | kk) != 0);
            WG_COMMIT();
            if (F0V == 2) { WG_WAIT(1); mbar_arrive_elect(ra); }
            mbar_wait(bar0 + (kBarFullX + 2 * k + 1) * 8, 0);
            WG_FENCE();
#pragma unroll
            for (int kk = 0; kk < 4; kk++) wgmma_ss_n136<1, 0>(acc, da + 512 + kk * 128, db + (kStage >> 4) + kk * 2, 1);
            WG_COMMIT();
            if (F0V == 1) { WG_WAIT(2); mbar_arrive_elect(ra); }
            ra = bar0 + (k < 3 ? kBarEmpty + 2 * k : kBarSpare) * 8;
          }
        } else {
          mbar_wait(bar0 + (kBarTurn + b + 1) * 8, 0);
#pragma unroll 1
          for (int k = 0; k < 4; k++) {
            const uint64_t da = desc2(sb16 + (kOffW >> 4) + k * 1024 + (512u << 16), kHi128);
            const uint64_t db = desc2(sb16 + k * (kStage >> 3) + (1u << 16), kHi128);
            mbar_wait(bar0 + (kBarFullA + 8 + 4 * b + k) * 8, 0);
            WG_FENCE();
#pragma unroll
            for (int kk = 0; kk < 8; kk++) wgmma_ss_n136<1, 0>(acc, da + kk * 128, db + (kk & 3) * 2 + (kk >> 2) * (kStage >> 4), 1);
            WG_COMMIT();
            WG_WAIT(1);
            mbar_arrive_elect2(ra);
            ra = bar0 + ((b == 2 ? kBarEmpty2 : kBarEmpty) + 2 * k) * 8;
          }
        }
        mbar_arrive_elect(bar0 + (kBarTurn + (b ? b + 2 : 0)) * 8);
        if (b == 0) small_loads();
        WG_WAIT(0);
        reg_fence(acc);
        mbar_arrive_elect2(ra);
        PROF(9 + b);
        if (!DUMMY && fb * 64 >= kF) break;
        ln_fixup(acc, bf_lo(__shfl_sync(0xffffffffu, bq, b & 2, 4)), bf_lo(__shfl_sync(0xffffffffu, bq, (b & 2) + 1, 4)), q, sb + kOffFix, bar0 + kBarStats * 8, sb, b < 2 ? 42 + b : 61);
        if (b < 2) PROF(b ? 36 : 41);
        if (F2_GO >= 0 && b == 2) mbar_wait(bar0 + (F2_GO == 99 ? kBarDone : kBarFull2 + F2_GO) * 8, 0);
        const int c = b ? fb + 8 : fb;
        uint4* dst = p.hid + (DUMMY && fb * 64 >= kF ? kTiles * kNCH + tile * 2 + (slice & 1) : tile * kNCH + c) * 1024 + w * 256 + g * 4 + (q ^ (g >> 1));
        const uint32_t pc = ((g & 1) * 4 + (q ^ (g >> 1))) ^ (g & 6), ta = pc == 0, tb = pc == 1, tv = ~epoch;
#pragma unroll
        for (int m = 0; m < 4; m++) {
          uint32_t pa[4], pb[4];
          float4 sc;
#pragma unroll
          for (int jj = 0; jj < 4; jj++) {
            const int j = 4 * m + jj;
            if (!(jj & 1)) sc = lds128(sb + kOffScl + q * 144 + j * 8);
            const float a0 = (jj & 1) ? sc.z : sc.x, a1 = (jj & 1) ? sc.w : sc.y;
            float z[4] = {acc[4 * j] * a0, acc[4 * j + 1] * a1, acc[4 * j + 2] * a0, acc[4 * j + 3] * a1};
#pragma unroll
            for (int e = 0; e < 4; e++) {
              const float E = ex2f(z[e]);
              const float r = rcpf(fmaf(E, fmaf(E, 0.5f, 1.f), 1.f));
              z[e] = fmaf(-z[e], r, z[e]);
            }
            pa[jj] = pack_bf16(z[0], z[1]);
            pb[jj] = pack_bf16(z[2], z[3]);
          }
          pa[m & 1] = (pa[m & 1] & ~ta) | (tv & ta);
          pb[m & 1] = (pb[m & 1] & ~tb) | (tv & tb);
          stg128(dst + m * 32, pa);
          stg128(dst + m * 32 + 128, pb);
          if (((MFENCE >> m) & 1) && m != 3) mbar_arrive_elect(bar0 + kBarSpare * 8);
        }
        PROF(12 + b);
        if (b == 1) mbar_arrive_elect(bar0 + kBarDone * 8);
      }
      asm volatile("setmaxnreg.dec.sync.aligned.u32 24;");
    } else {
    const int sblk = wgi;
    const uint32_t tag = ~epoch & 1;
    if (q == 3) asm volatile("st.relaxed.gpu.global.v2.u32 [%0], {%1,%1};" ::"l"(p.agg + bx * 64 + (tid >> 2)), "r"(tag ^ 1) : "memory");
    if ((warp >> 1) == 1) {
      const float lr = bf_lo(r_lr), li = bf_lo(r_li);
      const float dt = __bfloat162float(__float2bfloat16(expf(bf_lo(r_dt))));
      const float mag = expf(dt * lr);
      float sn, cs;
      sincospif(dt * li * 0.31830988618379067f, &sn, &cs);
      const float nr = mag * cs - 1.f, ni = mag * sn;
      const float sc = __fdividef(2.f * kLn2, lr * lr + li * li);
      const float kr = (nr * lr + ni * li) * sc, ki = (ni * lr - nr * li) * sc;
      float2 t = make_float2(mag * cs, p.swapB ? -ni : ni);
      const uint32_t a = sb + kOffCst + ((w & 1) * 32 + lane) * 16;
      const float2 cr = p.swapB ? make_float2(-ki, kr) : make_float2(kr, -ki);
      const float2 ci = p.swapB ? make_float2(-kr, -ki) : make_float2(-ki, -kr);
      if (p.swapC) sts128(a, ci.x, ci.y, cr.x, cr.y); else sts128(a, cr.x, cr.y, ci.x, ci.y);
      const float2 lam = t;
#pragma unroll 1
      for (int i = 0; i < 5; i++) t = cmul(t, t);
      const float2 l64 = cmul(t, t), l128 = cmul(l64, l64), l256 = cmul(l128, l128), l512 = cmul(l256, l256), l1024 = cmul(l512, l512);
      sts128(a + 1024, lam.x, lam.y, l128.x, l128.y);
      sts128(a + 2048, t.x, t.y, l64.x, l64.y);
      sts128(a + 3072, l512.x, l512.y, l1024.x, l1024.y);
      __syncwarp();
      mbar_arrive_elect(bar0 + (kBarTurn + 5) * 8);
      if (warp == 3) PROFW(1);
    }
    {
      float u[64];
      reg_define(u);
      if (sblk || !S0_FREE) mbar_wait(bar0 + (kBarTurn + sblk) * 8, 0);
      uint32_t ra = bar0 + kBarSpare * 8;
#pragma unroll 1
      for (int k = 0; k < 4; k++) {
        const uint64_t da = desc2(sb16 + (kOffW >> 4) + k * 1024 + (1u << 16), kHi128);
        const uint64_t db = desc2(sb16 + k * (kStage >> 3) + (1u << 16), kHi128);
        if (XTRA && S0_FREE && k == 3) mbar_wait(bar0 + kBarTurn * 8, 0);
        mbar_wait(bar0 + (kBarFullA + 4 + sblk * 4 + k) * 8, 0);
        WG_FENCE();
#pragma unroll
        for (int kk = 0; kk < 8; kk++)
          wgmma_ss_n128<0, 0>(u, da + (kk & 3) * 2 + (kk >> 2) * 512, db + (kk & 3) * 2 + (kk >> 2) * (kStage >> 4), 1);
        WG_COMMIT();
        WG_WAIT(1);
        mbar_arrive_elect(ra);
        ra = bar0 + (kBarEmpty + 2 * k) * 8;
      }
      mbar_arrive_elect(bar0 + (kBarTurn + 1 + sblk) * 8);
      mbar_wait(bar0 + (kBarTurn + 5) * 8, 0);
      WG_FENCE();
      wgmma_ss_n128<0, 0>(u, desc2(sb16 + (kOffFixA >> 4) + sblk * 64, 8), desc2(sb16 + (kOffFix >> 4), 8), 1);
      WG_COMMIT();
      WG_WAIT(0);
      reg_fence(u);
      mbar_arrive_elect(ra);
      PROF(3 + sblk);
      const uint32_t cst = sb + kOffCst + (warp * 8 + g) * 16;
      const float4 c1 = lds128(cst + 1024), c2 = lds128(cst + 2048);
      const float2 lam = make_float2(c1.x, c1.y), l32 = make_float2(c2.x, c2.y), l64 = make_float2(c2.z, c2.w);
      float2 hs = make_float2(0.f, 0.f);
#pragma unroll
      for (int j2 = 0; j2 < 8; j2++) {
        const float4 sc = lds128(sb + kOffScl + q * 144 + j2 * 16);
#pragma unroll
        for (int e = 0; e < 4; e++) {
          const float a = e == 0 ? sc.x : e == 1 ? sc.y : e == 2 ? sc.z : sc.w;
          const int i = 8 * j2 + 4 * (e >> 1) + (e & 1);
          u[i] *= a;
          u[i + 2] *= a;
          hs = cfma(lam, hs, make_float2(u[i], u[i + 2]));
        }
      }
      float2 t = make_float2(__shfl_up_sync(0xffffffffu, hs.x, 1, 4), __shfl_up_sync(0xffffffffu, hs.y, 1, 4));
      if (q >= 1) hs = cfma(l32, t, hs);
      t = make_float2(__shfl_up_sync(0xffffffffu, hs.x, 2, 4), __shfl_up_sync(0xffffffffu, hs.y, 2, 4));
      if (q >= 2) hs = cfma(l64, t, hs);
      float2* agg = p.agg + (tile * 8 + slice) * 64 + warp * 8 + g;
      if (q == 3)
        asm volatile("st.relaxed.gpu.global.v2.u32 [%0], {%1,%2};" ::"l"(agg), "r"((__float_as_uint(hs.x) & ~1u) | tag),
                     "r"((__float_as_uint(hs.y) & ~1u) | tag) : "memory");
      PROF(5 + sblk);
      t = make_float2(__shfl_up_sync(0xffffffffu, hs.x, 1, 4), __shfl_up_sync(0xffffffffu, hs.y, 1, 4));
      if (q == 0) t = make_float2(0.f, 0.f);
      uint32_t v[4][2];
      int it = 0;
      mbar_wait(bar0 + (sblk ? EV1 : EV0) * 8, 0);
#pragma unroll 1
      do {
        if (it) __nanosleep(SLEEP2);
        asm volatile(
            "{\n.reg .pred p0, p1, p2, p3;\n"
            "setp.gt.s32 p0, %10, 0;\nsetp.gt.s32 p1, %10, 1;\nsetp.gt.s32 p2, %10, 2;\nsetp.gt.s32 p3, %10, 3;\n"
            "mov.b32 %0, %9;\nmov.b32 %1, %9;\nmov.b32 %2, %9;\nmov.b32 %3, %9;\nmov.b32 %4, %9;\nmov.b32 %5, %9;\nmov.b32 %6, %9;\nmov.b32 %7, %9;\n"
            "@p0 ld.relaxed.gpu.global.v2.u32 {%0,%1}, [%8+-4096];\n@p1 ld.relaxed.gpu.global.v2.u32 {%2,%3}, [%8+-8192];\n"
            "@p2 ld.relaxed.gpu.global.v2.u32 {%4,%5}, [%8+-12288];\n@p3 ld.relaxed.gpu.global.v2.u32 {%6,%7}, [%8+-16384];\n}"
            : "=&r"(v[0][0]), "=&r"(v[0][1]), "=&r"(v[1][0]), "=&r"(v[1][1]), "=&r"(v[2][0]), "=&r"(v[2][1]), "=&r"(v[3][0]), "=&r"(v[3][1])
            : "l"(agg - q * 2048), "r"(tag), "r"(tile - 4 * q) : "memory");
        const uint32_t any = (v[0][0] | v[0][1] | v[1][0]) | (v[1][1] | v[2][0] | v[2][1]) | (v[3][0] | v[3][1]);
        const uint32_t all = (v[0][0] & v[0][1] & v[1][0]) & (v[1][1] & v[2][0] & v[2][1]) & (v[3][0] & v[3][1]);
        if (NOPOLL || !__any_sync(0xffffffffu, (tag ? ~all : any) & 1)) break;
      } while (++it < kSpinLimit);
      const float4 c4 = lds128(cst + 1024), c5 = lds128(cst + 2048), c3 = lds128(cst + 3072);
      float2 a = (q & 1) ? make_float2(c5.x, c5.y) : make_float2(1.f, 0.f);
      const float2 lq32 = (q & 2) ? cmul(a, make_float2(c5.z, c5.w)) : a;
      a = (q & 1) ? make_float2(c3.x, c3.y) : make_float2(1.f, 0.f);
      const float2 lq512 = (q & 2) ? cmul(a, make_float2(c3.z, c3.w)) : a;
      float2 cin = make_float2(__uint_as_float(v[3][0]), __uint_as_float(v[3][1]));
#pragma unroll
      for (int i = 2; i >= 0; i--)
        cin = cfma(make_float2(c4.z, c4.w), cin, make_float2(__uint_as_float(v[i][0]), __uint_as_float(v[i][1])));
      cin = cmul(cin, lq512);
      cin.x += __shfl_xor_sync(0xffffffffu, cin.x, 1);
      cin.y += __shfl_xor_sync(0xffffffffu, cin.y, 1);
      cin.x += __shfl_xor_sync(0xffffffffu, cin.x, 2);
      cin.y += __shfl_xor_sync(0xffffffffu, cin.y, 2);
      hs = cfma(lq32, cin, t);
      PROF(18 + sblk);
      const float4 kc = lds128(cst);
      uint4* dst = p.hid + (tile * kNCH + 8 + sblk * 22 + (slice & 6)) * 1024 + (slice & 1) * 512 + w * 128 + g * 4 + (q ^ (g >> 1));
      const uint32_t tm = ((g & 1) * 4 + (q ^ (g >> 1))) == (g & 6) + (w & 1);
#pragma unroll
      for (int m = 0; m < 4; m++) {
#pragma unroll
        for (int i = 0; i < 8; i++) {
          const int k = 16 * m + 4 * (i >> 1) + (i & 1);
          hs = cfma(lam, hs, make_float2(u[k], u[k + 2]));
          u[k] = hs.x;
          u[k + 2] = hs.y;
        }
#pragma unroll
        for (int h = 0; h < 2; h++) {
          float k0, k1;
          if (P2_UNROLL == 2 || h == 0) mbar_arrive_elect(bar0 + kBarSpare * 8);
          asm volatile("ld.shared.v2.f32 {%0,%1}, [%2];" : "=f"(k0), "=f"(k1) : "r"(cst + h * 8) : "memory");
          uint32_t pk[4];
#pragma unroll
          for (int jj = 0; jj < 4; jj++) {
            const int k = 16 * m + 4 * jj;
            pk[jj] = pack_bf16(fmaf(k0, u[k], k1 * u[k + 2]), fmaf(k0, u[k + 1], k1 * u[k + 3]));
          }
          pk[m & 1] = (pk[m & 1] & ~tm) | (tag & tm);
          stg128(dst + m * 32 + h * 1024, pk);
        }
      }
      PROF(32 + sblk);
    }
    if (sblk == 1) {
      mbar_wait(bar0 + kBarXo * 8, 0);
      if (NORM_EV) mbar_wait(bar0 + (kBarFull2 + NORM_EV) * 8, 0);
#pragma unroll 1
      for (int i = 0; i < 4; i++) {
        float sc, sf;
        asm volatile("ld.shared.v2.f32 {%0,%1}, [%2];" : "=f"(sc), "=f"(sf) : "r"(sb + kOffLN + (32 * w + 8 * i + g) * 8) : "memory");
#pragma unroll
        for (int h = 0; h < 2; h++) {
          const uint32_t a = sb + kOffXo + (32 * i + 8 * w + (lane & 7)) * 128 + (((h * 4 + (lane >> 3)) ^ (lane & 7)) << 4);
          uint32_t u[4];
          asm volatile("ldmatrix.sync.aligned.m8n8.x4.shared.b16 {%0,%1,%2,%3}, [%4];" : "=r"(u[0]), "=r"(u[1]), "=r"(u[2]), "=r"(u[3]) : "r"(a) : "memory");
#pragma unroll
          for (int e = 0; e < 4; e++) u[e] = pack_bf16(fmaf(sc, bf_lo(u[e]), sf), fmaf(sc, bf_hi(u[e]), sf));
          asm volatile("stmatrix.sync.aligned.m8n8.x4.shared.b16 [%0], {%1,%2,%3,%4};" ::"r"(a), "r"(u[0]), "r"(u[1]), "r"(u[2]), "r"(u[3]) : "memory");
        }
      }
      asm volatile("fence.proxy.async.shared::cta;" ::: "memory");
      __syncwarp();
      mbar_arrive_elect(bar0 + kBarXn * 8);
      PROF(38);
      asm volatile("setmaxnreg.dec.sync.aligned.u32 24;");
    } else {
      asm volatile("setmaxnreg.inc.sync.aligned.u32 160;");
      float accf[64], ts[64];
      reg_define(accf);
      reg_define(ts);
      uint32_t ra = bar0 + kBarSpare * 8;
      uint32_t rdy = 0;
      auto pair = [&](auto mode, float (&acc)[64], int u) {
        constexpr int M = decltype(mode)::value;
        const uint64_t da = desc2(sb16 + (kOffW >> 4) + (u & 3) * 1024 + ((M ? 1u : 512u) << 16), kHi128);
        const uint64_t db = desc2(sb16 + (u & 3) * (kStage >> 3) + (32u << 16), kHiH);
#pragma unroll
        for (int j = 0; j < 2; j++) {
          if (!rdy) mbar_wait(bar0 + (kBarFull2 + 2 * u + j) * 8, 0);
          if (w == 1) TR(3, 2 * u + j);
          WG_FENCE();
#pragma unroll
          for (int kk = 0; kk < 4; kk++)
            wgmma_ss_n128<1 - M, 1>(acc, da + j * 512 + kk * (M ? 2 : 128), db + kk * 256 + j * (kStage >> 4), 1);
          WG_COMMIT();
          rdy = mbar_test(bar0 + (kBarFull2 + 2 * u + j + 1) * 8);
          WG_WAIT(1);
          mbar_arrive_elect(ra);
          ra = bar0 + (kBarEmpty2 + (u & 3) * 2 + j) * 8;
        }
      };
      PROF(39);
      mbar_wait(bar0 + (kBarTurn + 4) * 8, 0);
      PROF(7);
#pragma unroll 1
      for (int u = 0; u < 4; u++) pair(std::integral_constant<int, 0>(), accf, u);
      PROF(26);
#pragma unroll 1
      for (int u = 4; u < 8; u++) pair(std::integral_constant<int, 1>(), ts, u);
      asm volatile("setmaxnreg.inc.sync.aligned.u32 232;");
#pragma unroll 1
      for (int u = 8; u < 15; u++) pair(std::integral_constant<int, 0>(), accf, u);
      PROF(37);
      const int hb = w >> 1;
      const uint32_t st = sb + 7 * kStage + hb * 8192;
      uint32_t sa[4];
#pragma unroll
      for (int v = 0; v < 4; v++) {
        const int dl = 16 * (w & 1) + 8 * (v >> 1) + g, tt = 2 * q + (v & 1);
        sa[v] = st + tt * 128 + (((dl >> 2) ^ tt) << 4) + (dl & 3) * 4;
      }
      float* og = p.out + (tile * 128 + 2 * q) * 512 + slice * 64 + w * 16 + g;
      auto piece = [&](int jp, float half_ln2) {
#pragma unroll
        for (int v = 0; v < 8; v++) {
          const float hf = accf[8 * jp + v] * half_ln2;
          accf[8 * jp + v] = fmaf(hf, tanhf_(hf), hf);
        }
        asm volatile("{\n.reg .pred P;\nsetp.eq.u32 P, %0, 0;\n"
                     "@P st.shared.v4.f32 [%0], {%1,%2,%3,%4};\n@P st.global.v4.f32 [%9], {%5,%6,%7,%8};\n}"
                     ::"r"(sa[jp & 3]), "f"(accf[8 * jp]), "f"(accf[8 * jp + 1]), "f"(accf[8 * jp + 2]), "f"(accf[8 * jp + 3]), "f"(accf[8 * jp + 4]),
                       "f"(accf[8 * jp + 5]), "f"(accf[8 * jp + 6]), "f"(accf[8 * jp + 7]), "l"(og) : "memory");
      };
#pragma unroll
      for (int c = 30; c < kNCH; c++) {
        const uint64_t da = desc2(sb16 + (kOffW >> 4) + (c & 7) * 512 + (1u << 16), kHi128);
        const uint64_t db = desc2(sb16 + (c & 7) * (kStage >> 4) + (32u << 16), kHiH);
        if (!rdy) mbar_wait(bar0 + (kBarFull2 + c) * 8, 0);
        WG_FENCE();
#pragma unroll
        for (int kk = 0; kk < 4; kk++) wgmma_ss_n128<0, 1>(ts, da + kk * 2, db + kk * 256, 1);
        WG_COMMIT();
        rdy = mbar_test(bar0 + (kBarFull2 + c + 1) * 8);
        if (c == 30) {
          WG_WAIT(1);
          mbar_arrive_elect(ra);
          reg_fence(accf);
        }
        if (c == 31 && SKIP_AT != 16) {
          WG_WAIT(1);
          mbar_arrive_elect(bar0 + (kBarEmpty2 + 6) * 8);
        }
        if (c == SKIP_AT) {
          {
            const uint32_t sh = (g & 1) * 16, on = (g >> 1) == q;
            const uint32_t dA = __shfl_sync(0xffffffffu, bq, 0, 4) << sh, dB = __shfl_sync(0xffffffffu, bq, 1, 4) << sh;
            uint32_t a0[4], a3[4];
#pragma unroll
            for (int kk = 0; kk < 4; kk++) { a0[kk] = (on && kk == w) ? dA : 0u; a3[kk] = (on && kk == w) ? dB : 0u; }
            mbar_wait(bar0 + kBarXn * 8, 0);
            WG_FENCE();
#pragma unroll
            for (int kk = 0; kk < 4; kk++)
              wgmma_rs_n128<0>(ts, a0[kk], 0u, 0u, a3[kk], desc2(sb16 + (kOffXo >> 4) + (1u << 16), kHi128) + kk * 2, 1);
          }
          WG_COMMIT();
        }
        if (c == 33 && QTMA) {
          WG_WAIT(2);
          mbar_arrive_elect(bar0 + (kBarEmpty2 + 7) * 8);
        }
        if (c - 30 < NPIECE) piece(PORDER(c - 30), __uint_as_float(__float_as_uint(0.5f * kLn2) | (rdy & (uint32_t)(p.swapC >> 1))));
      }
      uint32_t xr[32];
      mbar_wait(bar0 + kBarXr * 8, 0);
      auto load_x = [&](int half) {
#pragma unroll
        for (int jp = half; jp < 8; jp += 2)
          asm volatile("ldmatrix.sync.aligned.m8n8.x4.trans.shared.b16 {%0,%1,%2,%3}, [%4];"
                       : "=r"(xr[4 * jp]), "=r"(xr[4 * jp + 1]), "=r"(xr[4 * jp + 2]), "=r"(xr[4 * jp + 3])
                       : "r"(sb + kOffXr + (16 * jp + 8 * (lane >> 4) + (lane & 7)) * 128 + (((2 * w + ((lane >> 3) & 1)) ^ (lane & 7)) << 4)) : "memory");
      };
      load_x(0);
      auto xf = [&](int i) { return (i & 1) ? bf_hi(xr[i >> 1]) : bf_lo(xr[i >> 1]); };
      if (QTMA) mbar_wait(bar0 + (kBarEmpty2 + 7) * 8, 0);
      WG_WAIT(0);
      reg_fence(ts);
      PROF(27);
#pragma unroll
      for (int qt = 0; qt < 4; qt++) {
        if (qt == 1) {
          load_x(1);
#pragma unroll
          for (int i = NPIECE; i < 8; i++) piece(PORDER(i), 0.5f * kLn2);
        }
#pragma unroll
        for (int j4 = 0; j4 < 4; j4++) {
          const int jj = j4 * 4 + qt;
#pragma unroll
          for (int v = 0; v < 4; v++) {
            const float o = fmaf(ts[4 * jj + v], accf[4 * jj + v], xf(4 * jj + v));
            if ((QTMA >> qt) & 1) asm volatile("st.shared.f32 [%0], %1;" ::"r"(sa[v] + (qt * 4 + j4) * 1024), "f"(o) : "memory");
            else asm volatile("st.global.f32 [%0], %1;" ::"l"(og + (32 * qt + 8 * j4 + (v & 1)) * 512 + (v >> 1) * 8), "f"(o) : "memory");
          }
        }
        if ((QISS >> qt) & 1) {
          asm volatile("fence.proxy.async.shared::cta;" ::: "memory");
          asm volatile("bar.sync %0, 64;" ::"r"(6 + hb) : "memory");
          if ((tid & 63) == 0) {
#pragma unroll
            for (int r = qt; r >= 0 && (r == qt || !((QISS >> r) & 1)); r--)
              if ((QTMA >> r) & 1)
                asm volatile("cp.async.bulk.tensor.2d.global.shared::cta.bulk_group [%0, {%2, %3}], [%1];"
                             ::"l"(&tmOut), "r"(st + r * 4096), "r"(slice * 64 + hb * 32), "r"(tile * 128 + r * 32) : "memory");
          }
          if (qt == 0) PROF(52);
        }
      }
      PROF(34);
      if (w == 1) p.epoch[blockIdx.x * 32 + lane] = epoch + 1;
      if ((tid & 63) == 0) {
        asm volatile("cp.async.bulk.commit_group;" ::: "memory");
        asm volatile("cp.async.bulk.wait_group.read 0;" ::: "memory");
      }
      PROF(25);
    }
    }
  }
}

typedef CUresult (*EncodeFn)(CUtensorMap*, CUtensorMapDataType, cuuint32_t, void*, const cuuint64_t*, const cuuint64_t*,
                             const cuuint32_t*, const cuuint32_t*, CUtensorMapInterleave, CUtensorMapSwizzle,
                             CUtensorMapL2promotion, CUtensorMapFloatOOBfill);

static void make_map(EncodeFn enc, CUtensorMap* tm, CUtensorMapDataType dt, int rank, void* ptr, const cuuint64_t* dims,
                     const cuuint64_t* str, const cuuint32_t* box, CUtensorMapSwizzle swz = CU_TENSOR_MAP_SWIZZLE_128B) {
  const cuuint32_t es[5] = {1, 1, 1, 1, 1};
  CUresult r = enc(tm, dt, rank, ptr, dims, str, box, es, CU_TENSOR_MAP_INTERLEAVE_NONE, swz,
                   CU_TENSOR_MAP_L2_PROMOTION_L2_128B, CU_TENSOR_MAP_FLOAT_OOB_FILL_NONE);
  if (r != CUDA_SUCCESS) fprintf(stderr, "tensor map encode failed: %d\n", (int)r);
}

extern "C" void kernel_launch(void* const* d_in, const int* in_sizes, int n_in, void* d_out, int out_size) {
  (void)in_sizes; (void)n_in; (void)out_size;
  void* fn = nullptr;
  cudaDriverEntryPointQueryResult qr;
  cudaGetDriverEntryPoint("cuTensorMapEncodeTiled", &fn, cudaEnableDefault, &qr);
  EncodeFn enc = (EncodeFn)fn;
  const CUtensorMapDataType bf = CU_TENSOR_MAP_DATA_TYPE_BFLOAT16;
  CUtensorMap tmX, tmB, tmW1, tmC, tmW2, tmOut, tmXo;
  Params p;
  {
    const cuuint64_t dims[5] = {512, 2, 4, 16, 16}, str[4] = {1024, 32 * 1024, 2 * 1024, 128 * 1024};
    const cuuint32_t box[5] = {64, 2, 4, 16, 1};
    make_map(enc, &tmX, bf, 5, d_in[0], dims, str, box);
  }
  {
    const cuuint64_t dims[5] = {512, 8, 4, 4, 16}, str[4] = {1024, 32 * 1024, 8 * 1024, 128 * 1024};
    const cuuint32_t box[5] = {64, 8, 4, 4, 1};
    make_map(enc, &tmXo, bf, 5, d_in[0], dims, str, box);
  }
  {
    char *re = (char*)d_in[3], *im = (char*)d_in[4];
    p.swapB = im < re;
    const cuuint64_t dims[5] = {64, 8, 2, 64, 8}, str[4] = {1024, (cuuint64_t)(p.swapB ? re - im : im - re), 8192, 128};
    const cuuint32_t box[5] = {64, 8, 2, 4, 2};
    make_map(enc, &tmB, bf, 5, p.swapB ? im : re, dims, str, box);
  }
  {
    char *re = (char*)d_in[5], *im = (char*)d_in[6];
    p.swapC = im < re;
    const cuuint64_t dims[3] = {512, 512, 2}, str[2] = {1024, (cuuint64_t)(p.swapC ? re - im : im - re)};
    const cuuint32_t box[3] = {64, 64, 1};
    make_map(enc, &tmC, bf, 3, p.swapC ? im : re, dims, str, box);
  }
  {
    const cuuint64_t dims[2] = {kF, 512}, str[1] = {kF * 2};
    const cuuint32_t box[2] = {64, 128};
    make_map(enc, &tmW1, bf, 2, d_in[10], dims, str, box);
  }
  {
    const cuuint64_t dims[3] = {512, kF, 1}, str[2] = {1024, 1024 * kF};
    const cuuint32_t box[3] = {64, 64, 1};
    make_map(enc, &tmW2, bf, 3, d_in[12], dims, str, box);
  }
  {
    const cuuint64_t dims[2] = {512, kL}, str[1] = {2048};
    const cuuint32_t box[2] = {32, 32};
    make_map(enc, &tmOut, CU_TENSOR_MAP_DATA_TYPE_FLOAT32, 2, d_out, dims, str, box);
  }
  cudaGetSymbolAddress((void**)&p.hid, g_hid);
  cudaGetSymbolAddress((void**)&p.agg, g_agg);
  cudaGetSymbolAddress((void**)&p.stat, g_stat);
  p.out = (float*)d_out;
  cudaGetSymbolAddress((void**)&p.wsum, g_wsum);
  cudaGetSymbolAddress((void**)&p.epoch, g_epoch);
  p.lam_re = (const __nv_bfloat16*)d_in[1];
  p.lam_im = (const __nv_bfloat16*)d_in[2];
  p.log_dt = (const __nv_bfloat16*)d_in[7];
  p.dskip = (const __nv_bfloat16*)d_in[8];
  p.b1 = (const __nv_bfloat16*)d_in[11];
  p.w1 = (const __nv_bfloat16*)d_in[10];
  p.w2 = (const __nv_bfloat16*)d_in[12];
  p.c_re = (const __nv_bfloat16*)d_in[5];
  p.c_im = (const __nv_bfloat16*)d_in[6];
  p.b_re = (const __nv_bfloat16*)d_in[3];
  p.b_im = (const __nv_bfloat16*)d_in[4];
  cudaFuncSetAttribute(s5_mish_fused_kernel, cudaFuncAttributeMaxDynamicSharedMemorySize, kSmemBytes);
  s5_mish_fused_kernel<<<128, 640, kSmemBytes>>>(p, tmX, tmW1, tmB, tmC, tmW2, tmOut, tmXo);
}
```
